```python
import torch

def _softmax(x, axis=-1):
    return torch.softmax(x, dim=axis)
def _gelu(x):
    return torch.nn.functional.gelu(x, approximate="tanh")
def _silu(x):
    return torch.nn.functional.silu(x)
def _sigmoid(x):
    return torch.sigmoid(x)
def _layernorm(x, axis=-1, eps=1e-5):
    m = x.mean(dim=axis, keepdim=True)
    v = x.var(dim=axis, keepdim=True, unbiased=False)
    return (x - m) / torch.sqrt(v + eps)
def _scatter_add(tgt, idx, src, axis=0):
    return tgt.clone().index_add_(axis, idx, src)
def _segment_sum(src, seg, n):
    out = torch.zeros((n,) + src.shape[1:], dtype=src.dtype)
    return out.index_add_(0, seg, src)
def _pad(x, pw):
    flat = tuple(v for pair in reversed(pw) for v in pair)
    return torch.nn.functional.pad(x, flat)

kernel_name = 'standalone__linear_kernel_performer__prompt'

def setup_inputs():

    _w = (lambda a: (lambda t: t.to(torch.bfloat16) if t.is_floating_point() else t)(torch.as_tensor(a)))
    B, H, S, D = 1, 16, 2048, 256
    M = D
    return {
        "q": _w((lambda *s: torch.randn(*s, dtype=torch.bfloat16) * 0.05)(B, H, S, D)),
        "k": _w((lambda *s: torch.randn(*s, dtype=torch.bfloat16) * 0.4)(B, H, S, D)),
        "v": _w((lambda *s: torch.randn(*s, dtype=torch.bfloat16) * 0.4)(B, H, S, D)),
        "proj": _w((lambda *s: torch.randn(*s, dtype=torch.bfloat16) * 0.4)(M, D)),
    }

def reference(q, k, v, proj):
    B, H, S, D = q.shape
    M = proj.shape[0]
    scale = D ** -0.25
    qs = q * scale
    ks = k * scale
    qw = torch.einsum("bhsd,md->bhsm", qs, proj)
    kw = torch.einsum("bhsd,md->bhsm", ks, proj)
    qn = torch.einsum("bhsd,bhsd->bhs", qs, qs)[..., None] * 0.5
    kn = torch.einsum("bhsd,bhsd->bhs", ks, ks)[..., None] * 0.5
    inv_sqrt_m = M ** -0.5
    phi_q = torch.exp(qw - qn) * inv_sqrt_m
    phi_k = torch.exp(kw - kn) * inv_sqrt_m
    kv = torch.einsum("bhsm,bhsd->bhmd", phi_k, v)
    ksum = torch.einsum("bhsm->bhm", phi_k)
    num = torch.einsum("bhsm,bhmd->bhsd", phi_q, kv)
    den = torch.einsum("bhsm,bhm->bhs", phi_q, ksum)[..., None] + 1e-6
    return num / den
```

```cpp
#include <cuda_runtime.h>
#include <cuda_bf16.h>
#include <cuda.h>
#include <stdint.h>

namespace {

constexpr int kHeads = 16, kSeq = 2048, kDim = 256;
constexpr int kThreads = 384;

constexpr uint32_t OFF_PROJ = 0;
constexpr uint32_t OFF_X0 = 131072;
constexpr uint32_t OFF_X1 = 163840;
constexpr uint32_t OFF_X2 = 196608;
constexpr uint32_t OFF_BAR = 229376;
constexpr uint32_t OFF_KSUM = OFF_BAR + 512;
constexpr uint32_t OFF_KN = OFF_KSUM + 512;
constexpr uint32_t SMEM_BYTES = OFF_KN + 2048;

enum : uint32_t {
  B_FULLK = 0, B_FULLV = 8, B_EMPTYK = 16, B_EMPTYV = 24, B_KN = 32, B_PROJA = 40, B_PROJB = 41,
  B_FULLQ = 42, B_EMPTYQ = 46, B_QN = 50, B_KV = 54, B_STG = 58, B_QLO = 62,
  B_FULLQH = B_FULLK
};
constexpr int kTurnBar = 2;

constexpr float kLog2e = 1.4426950408889634f;
constexpr float kDotScale = 0.25f * kLog2e;
constexpr float kNormScale = kLog2e / 32.0f;
constexpr float kFeatShift = 4.0f;
constexpr uint32_t kSpinLimit = 1u << 20;

__device__ uint4 g_kv[kHeads * 8192];
__device__ __nv_bfloat16 g_ksum[kHeads * 256];
__device__ unsigned g_flag[kHeads * 4];
__device__ unsigned g_epoch[128];

__device__ __forceinline__ uint32_t smem_u32(const void* p) { return (uint32_t)__cvta_generic_to_shared(p); }

__device__ __forceinline__ void mbar_init(uint32_t bar, uint32_t cnt) {
  asm volatile("mbarrier.init.shared::cta.b64 [%0], %1;" ::"r"(bar), "r"(cnt) : "memory");
}
__device__ __forceinline__ void mbar_expect_tx(uint32_t bar, uint32_t bytes) {
  asm volatile("mbarrier.arrive.expect_tx.shared::cta.b64 _, [%0], %1;" ::"r"(bar), "r"(bytes) : "memory");
}
__device__ __forceinline__ void mbar_arrive(uint32_t bar) {
  asm volatile("mbarrier.arrive.shared::cta.b64 _, [%0];" ::"r"(bar) : "memory");
}
template <int kParity = 0>
__device__ __forceinline__ void mbar_wait(uint32_t bar) {
  asm volatile("{ .reg .pred p; .reg .u32 n; mov.u32 n, 0;\n"
               "W_%=: mbarrier.try_wait.parity.shared::cta.b64 p, [%0], %2;\n"
               "@p bra D_%=; add.u32 n, n, 1; setp.lt.u32 p, n, %1; @p bra W_%=;\n"
               "D_%=: }" ::"r"(bar), "n"(kSpinLimit), "n"(kParity) : "memory");
}
template <int kParity = 0>
__device__ __forceinline__ void mbar_wait_warp(uint32_t bar) {
  mbar_wait<kParity>(bar);
  __syncwarp();
}
__device__ __forceinline__ void flag_wait(const unsigned* p, unsigned target) {
  asm volatile("{ .reg .pred p; .reg .u32 n, v; mov.u32 n, 0;\n"
               "W_%=: ld.acquire.gpu.global.u32 v, [%0]; sub.u32 v, v, %1; setp.ge.s32 p, v, 0;\n"
               "@p bra D_%=; add.u32 n, n, 1; setp.lt.u32 p, n, %2; @p bra W_%=;\n"
               "D_%=: }" ::"l"(p), "r"(target), "n"(kSpinLimit) : "memory");
}
__device__ __forceinline__ void flag_publish(unsigned* p) {
  asm volatile("red.release.gpu.global.add.u32 [%0], 1;" ::"l"(p) : "memory");
}
__device__ __forceinline__ void tma_box(uint32_t dst, const CUtensorMap* m, int col, int row, uint32_t bar) {
  asm volatile("cp.async.bulk.tensor.2d.shared::cluster.global.mbarrier::complete_tx::bytes [%0], [%1, {%3, %4}], [%2];"
               ::"r"(dst), "l"(m), "r"(bar), "r"(col), "r"(row) : "memory");
}
__device__ __forceinline__ uint64_t stream_policy() {
  uint64_t pol;
  asm volatile("createpolicy.fractional.L2::evict_first.b64 %0, 1.0;" : "=l"(pol));
  return pol;
}
template <bool kStream>
__device__ __forceinline__ void tma_tile(uint32_t dst, uint32_t stride, const CUtensorMap* m, int row, uint32_t bar) {
  mbar_expect_tx(bar, 32768);
#pragma unroll
  for (int j = 0; j < 4; j++) {
    if (kStream)
      asm volatile("cp.async.bulk.tensor.2d.shared::cluster.global.mbarrier::complete_tx::bytes.L2::cache_hint [%0], [%1, {%3, %4}], [%2], %5;"
                   ::"r"(dst + j * stride), "l"(m), "r"(bar), "r"(j * 64), "r"(row), "l"(stream_policy()) : "memory");
    else
      tma_box(dst + j * stride, m, j * 64, row, bar);
  }
}
__device__ __forceinline__ void tma_tile3(uint32_t dst, const CUtensorMap* m, int row, uint32_t bar) {
  mbar_expect_tx(bar, 32768);
  const uint64_t pol = stream_policy();
  asm volatile("cp.async.bulk.tensor.3d.shared::cluster.global.mbarrier::complete_tx::bytes.L2::cache_hint [%0], [%1, {%3, %4, %3}], [%2], %5;"
               ::"r"(dst), "l"(m), "r"(bar), "r"(0), "r"(row), "l"(pol) : "memory");
}
__device__ __forceinline__ void tma_half_tile(uint32_t dst, const CUtensorMap* m, int row, int slab0, uint32_t bar) {
  mbar_expect_tx(bar, 16384);
  asm volatile("cp.async.bulk.tensor.3d.shared::cluster.global.mbarrier::complete_tx::bytes.L2::cache_hint [%0], [%1, {%3, %4, %5}], [%2], %6;"
               ::"r"(dst), "l"(m), "r"(bar), "r"(0), "r"(row), "r"(slab0), "l"(stream_policy()) : "memory");
}
__device__ __forceinline__ void bulk_load(uint32_t dst, const void* src, uint32_t bytes, uint32_t bar) {
  asm volatile("cp.async.bulk.shared::cluster.global.mbarrier::complete_tx::bytes [%0], [%1], %2, [%3];"
               ::"r"(dst), "l"(src), "r"(bytes), "r"(bar) : "memory");
}
__device__ __forceinline__ void bulk_store(void* dst, uint32_t src, uint32_t bytes) {
  asm volatile("cp.async.bulk.global.shared::cta.bulk_group [%0], [%1], %2;" ::"l"(dst), "r"(src), "r"(bytes) : "memory");
}
__device__ __forceinline__ void bulk_reduce_bf16(void* dst, uint32_t src, uint32_t bytes) {
  asm volatile("cp.reduce.async.bulk.global.shared::cta.bulk_group.add.noftz.bf16 [%0], [%1], %2;"
               ::"l"(dst), "r"(src), "r"(bytes) : "memory");
}
__device__ __forceinline__ void bulk_commit() { asm volatile("cp.async.bulk.commit_group;" ::: "memory"); }
template <int kPending = 0>
__device__ __forceinline__ void bulk_wait_read() { asm volatile("cp.async.bulk.wait_group.read %0;" ::"n"(kPending) : "memory"); }
__device__ __forceinline__ void bulk_wait_all() { asm volatile("cp.async.bulk.wait_group 0;" ::: "memory"); }
__device__ __forceinline__ void fence_async_smem() { asm volatile("fence.proxy.async.shared::cta;" ::: "memory"); }
__device__ __forceinline__ void turn_wait(int w) {
  if (w == 0) asm volatile("bar.sync %0, 256;" ::"n"(kTurnBar) : "memory");
  else asm volatile("bar.sync %0, 256;" ::"n"(kTurnBar + 1) : "memory");
}
__device__ __forceinline__ void turn_pass(int w) {
  if (w == 0) asm volatile("bar.arrive %0, 256;" ::"n"(kTurnBar + 1) : "memory");
  else asm volatile("bar.arrive %0, 256;" ::"n"(kTurnBar) : "memory");
}
__device__ __forceinline__ float rcp(float x) {
  float y;
  asm("rcp.approx.ftz.f32 %0, %1;" : "=f"(y) : "f"(x));
  return y;
}
__device__ __forceinline__ void wg_fence() { asm volatile("wgmma.fence.sync.aligned;" ::: "memory"); }
__device__ __forceinline__ void wg_commit() { asm volatile("wgmma.commit_group.sync.aligned;" ::: "memory"); }
__device__ __forceinline__ void wg_wait0() { asm volatile("wgmma.wait_group.sync.aligned 0;" ::: "memory"); }
__device__ __forceinline__ void wg_wait1() { asm volatile("wgmma.wait_group.sync.aligned 1;" ::: "memory"); }

template <int N> __device__ __forceinline__ void pin(float (&r)[N]) {
#pragma unroll
  for (int i = 0; i < N; i++) asm volatile("" : "+f"(r[i])::"memory");
}

__device__ __forceinline__ uint64_t make_desc(uint32_t addr, uint32_t lbo, uint32_t sbo) {
  const uint32_t lo = ((addr & 0x3FFFF) >> 4) | ((lbo >> 4) << 16);
  const uint32_t hi = (sbo >> 4) | (1u << 30);
  return ((uint64_t)hi << 32) | lo;
}
__device__ __forceinline__ uint64_t make_vec_desc(uint32_t addr) {
  return ((uint64_t)8 << 32) | ((addr & 0x3FFFF) >> 4) | (1u << 16);
}
__device__ __forceinline__ uint64_t desc_add(uint64_t d, uint32_t bytes) { return d + (uint64_t)(bytes >> 4); }

__device__ __forceinline__ float ex2(float x) {
  float y;
  asm("ex2.approx.ftz.f32 %0, %1;" : "=f"(y) : "f"(x));
  return y;
}
__device__ __forceinline__ uint32_t pack_bf16(float lo, float hi) {
  uint32_t r;
  asm("cvt.rn.bf16x2.f32 %0, %1, %2;" : "=r"(r) : "f"(hi), "f"(lo));
  return r;
}
__device__ __forceinline__ float bf_lo(uint32_t w) { return __uint_as_float(w << 16); }
__device__ __forceinline__ float bf_hi(uint32_t w) { return __uint_as_float(w & 0xffff0000u); }
__device__ __forceinline__ uint4 lds128(uint32_t a) {
  uint4 v;
  asm volatile("ld.shared.v4.u32 {%0, %1, %2, %3}, [%4];" : "=r"(v.x), "=r"(v.y), "=r"(v.z), "=r"(v.w) : "r"(a));
  return v;
}
__device__ __forceinline__ float2 lds64f(uint32_t a) {
  float2 v;
  asm volatile("ld.shared.v2.f32 {%0, %1}, [%2];" : "=f"(v.x), "=f"(v.y) : "r"(a));
  return v;
}
__device__ __forceinline__ float lds32f(uint32_t a) {
  float v;
  asm volatile("ld.shared.f32 %0, [%1];" : "=f"(v) : "r"(a));
  return v;
}
__device__ __forceinline__ void sts128(uint32_t a, uint32_t x, uint32_t y, uint32_t z, uint32_t w) {
  asm volatile("st.shared.v4.u32 [%0], {%1, %2, %3, %4};" ::"r"(a), "r"(x), "r"(y), "r"(z), "r"(w) : "memory");
}

__device__ __forceinline__ void wgmma_ss_n64(float (&d)[32], uint64_t da, uint64_t db) {
  asm volatile("{ .reg .pred p; setp.ne.b32 p, 1, 0;\n"
    "wgmma.mma_async.sync.aligned.m64n64k16.f32.bf16.bf16 "
    "{%0, %1, %2, %3, %4, %5, %6, %7, %8, %9, %10, %11, %12, %13, %14, %15, %16, %17, %18, %19, %20, %21, %22, %23, %24, %25, %26, %27, %28, %29, %30, "
    "%31}, "
    "%32, %33, p, 1, 1, 0, 0; }"
    : "+f"(d[0]), "+f"(d[1]), "+f"(d[2]), "+f"(d[3]), "+f"(d[4]), "+f"(d[5]), "+f"(d[6]), "+f"(d[7]), "+f"(d[8]), "+f"(d[9]), "+f"(d[10]), "+f"(d[11]),
      "+f"(d[12]), "+f"(d[13]), "+f"(d[14]), "+f"(d[15]), "+f"(d[16]), "+f"(d[17]), "+f"(d[18]), "+f"(d[19]), "+f"(d[20]), "+f"(d[21]), "+f"(d[22]),
      "+f"(d[23]), "+f"(d[24]), "+f"(d[25]), "+f"(d[26]), "+f"(d[27]), "+f"(d[28]), "+f"(d[29]), "+f"(d[30]), "+f"(d[31])
    : "l"(da), "l"(db));
}
__device__ __forceinline__ void wgmma_ss_n256_init(float (&d)[128], uint64_t da, uint64_t db) {
  asm volatile("{ .reg .pred p; setp.ne.b32 p, 0, 0;\n"
    "wgmma.mma_async.sync.aligned.m64n256k16.f32.bf16.bf16 "
    "{%0, %1, %2, %3, %4, %5, %6, %7, %8, %9, %10, %11, %12, %13, %14, %15, %16, %17, %18, %19, %20, %21, %22, %23, %24, %25, %26, %27, %28, %29, %30, %31, "
    "%32, %33, %34, %35, %36, %37, %38, %39, %40, %41, %42, %43, %44, %45, %46, %47, %48, %49, %50, %51, %52, %53, %54, %55, %56, %57, %58, %59, %60, %61, "
    "%62, %63, %64, %65, %66, %67, %68, %69, %70, %71, %72, %73, %74, %75, %76, %77, %78, %79, %80, %81, %82, %83, %84, %85, %86, %87, %88, %89, %90, %91, "
    "%92, %93, %94, %95, %96, %97, %98, %99, %100, %101, %102, %103, %104, %105, %106, %107, %108, %109, %110, %111, %112, %113, %114, %115, %116, %117, "
    "%118, %119, %120, %121, %122, %123, %124, %125, %126, %127}, "
    "%128, %129, p, 1, 1, 0, 0; }"
    : "=f"(d[0]), "=f"(d[1]), "=f"(d[2]), "=f"(d[3]), "=f"(d[4]), "=f"(d[5]), "=f"(d[6]), "=f"(d[7]), "=f"(d[8]), "=f"(d[9]), "=f"(d[10]), "=f"(d[11]),
      "=f"(d[12]), "=f"(d[13]), "=f"(d[14]), "=f"(d[15]), "=f"(d[16]), "=f"(d[17]), "=f"(d[18]), "=f"(d[19]), "=f"(d[20]), "=f"(d[21]), "=f"(d[22]),
      "=f"(d[23]), "=f"(d[24]), "=f"(d[25]), "=f"(d[26]), "=f"(d[27]), "=f"(d[28]), "=f"(d[29]), "=f"(d[30]), "=f"(d[31]), "=f"(d[32]), "=f"(d[33]),
      "=f"(d[34]), "=f"(d[35]), "=f"(d[36]), "=f"(d[37]), "=f"(d[38]), "=f"(d[39]), "=f"(d[40]), "=f"(d[41]), "=f"(d[42]), "=f"(d[43]), "=f"(d[44]),
      "=f"(d[45]), "=f"(d[46]), "=f"(d[47]), "=f"(d[48]), "=f"(d[49]), "=f"(d[50]), "=f"(d[51]), "=f"(d[52]), "=f"(d[53]), "=f"(d[54]), "=f"(d[55]),
      "=f"(d[56]), "=f"(d[57]), "=f"(d[58]), "=f"(d[59]), "=f"(d[60]), "=f"(d[61]), "=f"(d[62]), "=f"(d[63]), "=f"(d[64]), "=f"(d[65]), "=f"(d[66]),
      "=f"(d[67]), "=f"(d[68]), "=f"(d[69]), "=f"(d[70]), "=f"(d[71]), "=f"(d[72]), "=f"(d[73]), "=f"(d[74]), "=f"(d[75]), "=f"(d[76]), "=f"(d[77]),
      "=f"(d[78]), "=f"(d[79]), "=f"(d[80]), "=f"(d[81]), "=f"(d[82]), "=f"(d[83]), "=f"(d[84]), "=f"(d[85]), "=f"(d[86]), "=f"(d[87]), "=f"(d[88]),
      "=f"(d[89]), "=f"(d[90]), "=f"(d[91]), "=f"(d[92]), "=f"(d[93]), "=f"(d[94]), "=f"(d[95]), "=f"(d[96]), "=f"(d[97]), "=f"(d[98]), "=f"(d[99]),
      "=f"(d[100]), "=f"(d[101]), "=f"(d[102]), "=f"(d[103]), "=f"(d[104]), "=f"(d[105]), "=f"(d[106]), "=f"(d[107]), "=f"(d[108]), "=f"(d[109]),
      "=f"(d[110]), "=f"(d[111]), "=f"(d[112]), "=f"(d[113]), "=f"(d[114]), "=f"(d[115]), "=f"(d[116]), "=f"(d[117]), "=f"(d[118]), "=f"(d[119]),
      "=f"(d[120]), "=f"(d[121]), "=f"(d[122]), "=f"(d[123]), "=f"(d[124]), "=f"(d[125]), "=f"(d[126]), "=f"(d[127])
    : "l"(da), "l"(db));
}
__device__ __forceinline__ void wgmma_ss_n256(float (&d)[128], uint64_t da, uint64_t db) {
  asm volatile("{ .reg .pred p; setp.ne.b32 p, 1, 0;\n"
    "wgmma.mma_async.sync.aligned.m64n256k16.f32.bf16.bf16 "
    "{%0, %1, %2, %3, %4, %5, %6, %7, %8, %9, %10, %11, %12, %13, %14, %15, %16, %17, %18, %19, %20, %21, %22, %23, %24, %25, %26, %27, %28, %29, %30, %31, "
    "%32, %33, %34, %35, %36, %37, %38, %39, %40, %41, %42, %43, %44, %45, %46, %47, %48, %49, %50, %51, %52, %53, %54, %55, %56, %57, %58, %59, %60, %61, "
    "%62, %63, %64, %65, %66, %67, %68, %69, %70, %71, %72, %73, %74, %75, %76, %77, %78, %79, %80, %81, %82, %83, %84, %85, %86, %87, %88, %89, %90, %91, "
    "%92, %93, %94, %95, %96, %97, %98, %99, %100, %101, %102, %103, %104, %105, %106, %107, %108, %109, %110, %111, %112, %113, %114, %115, %116, %117, "
    "%118, %119, %120, %121, %122, %123, %124, %125, %126, %127}, "
    "%128, %129, p, 1, 1, 0, 0; }"
    : "+f"(d[0]), "+f"(d[1]), "+f"(d[2]), "+f"(d[3]), "+f"(d[4]), "+f"(d[5]), "+f"(d[6]), "+f"(d[7]), "+f"(d[8]), "+f"(d[9]), "+f"(d[10]), "+f"(d[11]),
      "+f"(d[12]), "+f"(d[13]), "+f"(d[14]), "+f"(d[15]), "+f"(d[16]), "+f"(d[17]), "+f"(d[18]), "+f"(d[19]), "+f"(d[20]), "+f"(d[21]), "+f"(d[22]),
      "+f"(d[23]), "+f"(d[24]), "+f"(d[25]), "+f"(d[26]), "+f"(d[27]), "+f"(d[28]), "+f"(d[29]), "+f"(d[30]), "+f"(d[31]), "+f"(d[32]), "+f"(d[33]),
      "+f"(d[34]), "+f"(d[35]), "+f"(d[36]), "+f"(d[37]), "+f"(d[38]), "+f"(d[39]), "+f"(d[40]), "+f"(d[41]), "+f"(d[42]), "+f"(d[43]), "+f"(d[44]),
      "+f"(d[45]), "+f"(d[46]), "+f"(d[47]), "+f"(d[48]), "+f"(d[49]), "+f"(d[50]), "+f"(d[51]), "+f"(d[52]), "+f"(d[53]), "+f"(d[54]), "+f"(d[55]),
      "+f"(d[56]), "+f"(d[57]), "+f"(d[58]), "+f"(d[59]), "+f"(d[60]), "+f"(d[61]), "+f"(d[62]), "+f"(d[63]), "+f"(d[64]), "+f"(d[65]), "+f"(d[66]),
      "+f"(d[67]), "+f"(d[68]), "+f"(d[69]), "+f"(d[70]), "+f"(d[71]), "+f"(d[72]), "+f"(d[73]), "+f"(d[74]), "+f"(d[75]), "+f"(d[76]), "+f"(d[77]),
      "+f"(d[78]), "+f"(d[79]), "+f"(d[80]), "+f"(d[81]), "+f"(d[82]), "+f"(d[83]), "+f"(d[84]), "+f"(d[85]), "+f"(d[86]), "+f"(d[87]), "+f"(d[88]),
      "+f"(d[89]), "+f"(d[90]), "+f"(d[91]), "+f"(d[92]), "+f"(d[93]), "+f"(d[94]), "+f"(d[95]), "+f"(d[96]), "+f"(d[97]), "+f"(d[98]), "+f"(d[99]),
      "+f"(d[100]), "+f"(d[101]), "+f"(d[102]), "+f"(d[103]), "+f"(d[104]), "+f"(d[105]), "+f"(d[106]), "+f"(d[107]), "+f"(d[108]), "+f"(d[109]),
      "+f"(d[110]), "+f"(d[111]), "+f"(d[112]), "+f"(d[113]), "+f"(d[114]), "+f"(d[115]), "+f"(d[116]), "+f"(d[117]), "+f"(d[118]), "+f"(d[119]),
      "+f"(d[120]), "+f"(d[121]), "+f"(d[122]), "+f"(d[123]), "+f"(d[124]), "+f"(d[125]), "+f"(d[126]), "+f"(d[127])
    : "l"(da), "l"(db));
}
__device__ __forceinline__ void wgmma_rs_n256(float (&d)[128], uint32_t a0, uint32_t a1, uint32_t a2, uint32_t a3, uint64_t db) {
  asm volatile("{ .reg .pred p; setp.ne.b32 p, 1, 0;\n"
    "wgmma.mma_async.sync.aligned.m64n256k16.f32.bf16.bf16 "
    "{%0, %1, %2, %3, %4, %5, %6, %7, %8, %9, %10, %11, %12, %13, %14, %15, %16, %17, %18, %19, %20, %21, %22, %23, %24, %25, %26, %27, %28, %29, %30, %31, "
    "%32, %33, %34, %35, %36, %37, %38, %39, %40, %41, %42, %43, %44, %45, %46, %47, %48, %49, %50, %51, %52, %53, %54, %55, %56, %57, %58, %59, %60, %61, "
    "%62, %63, %64, %65, %66, %67, %68, %69, %70, %71, %72, %73, %74, %75, %76, %77, %78, %79, %80, %81, %82, %83, %84, %85, %86, %87, %88, %89, %90, %91, "
    "%92, %93, %94, %95, %96, %97, %98, %99, %100, %101, %102, %103, %104, %105, %106, %107, %108, %109, %110, %111, %112, %113, %114, %115, %116, %117, "
    "%118, %119, %120, %121, %122, %123, %124, %125, %126, %127}, "
    "{%128, %129, %130, %131}, %132, p, 1, 1, 1; }"
    : "+f"(d[0]), "+f"(d[1]), "+f"(d[2]), "+f"(d[3]), "+f"(d[4]), "+f"(d[5]), "+f"(d[6]), "+f"(d[7]), "+f"(d[8]), "+f"(d[9]), "+f"(d[10]), "+f"(d[11]),
      "+f"(d[12]), "+f"(d[13]), "+f"(d[14]), "+f"(d[15]), "+f"(d[16]), "+f"(d[17]), "+f"(d[18]), "+f"(d[19]), "+f"(d[20]), "+f"(d[21]), "+f"(d[22]),
      "+f"(d[23]), "+f"(d[24]), "+f"(d[25]), "+f"(d[26]), "+f"(d[27]), "+f"(d[28]), "+f"(d[29]), "+f"(d[30]), "+f"(d[31]), "+f"(d[32]), "+f"(d[33]),
      "+f"(d[34]), "+f"(d[35]), "+f"(d[36]), "+f"(d[37]), "+f"(d[38]), "+f"(d[39]), "+f"(d[40]), "+f"(d[41]), "+f"(d[42]), "+f"(d[43]), "+f"(d[44]),
      "+f"(d[45]), "+f"(d[46]), "+f"(d[47]), "+f"(d[48]), "+f"(d[49]), "+f"(d[50]), "+f"(d[51]), "+f"(d[52]), "+f"(d[53]), "+f"(d[54]), "+f"(d[55]),
      "+f"(d[56]), "+f"(d[57]), "+f"(d[58]), "+f"(d[59]), "+f"(d[60]), "+f"(d[61]), "+f"(d[62]), "+f"(d[63]), "+f"(d[64]), "+f"(d[65]), "+f"(d[66]),
      "+f"(d[67]), "+f"(d[68]), "+f"(d[69]), "+f"(d[70]), "+f"(d[71]), "+f"(d[72]), "+f"(d[73]), "+f"(d[74]), "+f"(d[75]), "+f"(d[76]), "+f"(d[77]),
      "+f"(d[78]), "+f"(d[79]), "+f"(d[80]), "+f"(d[81]), "+f"(d[82]), "+f"(d[83]), "+f"(d[84]), "+f"(d[85]), "+f"(d[86]), "+f"(d[87]), "+f"(d[88]),
      "+f"(d[89]), "+f"(d[90]), "+f"(d[91]), "+f"(d[92]), "+f"(d[93]), "+f"(d[94]), "+f"(d[95]), "+f"(d[96]), "+f"(d[97]), "+f"(d[98]), "+f"(d[99]),
      "+f"(d[100]), "+f"(d[101]), "+f"(d[102]), "+f"(d[103]), "+f"(d[104]), "+f"(d[105]), "+f"(d[106]), "+f"(d[107]), "+f"(d[108]), "+f"(d[109]),
      "+f"(d[110]), "+f"(d[111]), "+f"(d[112]), "+f"(d[113]), "+f"(d[114]), "+f"(d[115]), "+f"(d[116]), "+f"(d[117]), "+f"(d[118]), "+f"(d[119]),
      "+f"(d[120]), "+f"(d[121]), "+f"(d[122]), "+f"(d[123]), "+f"(d[124]), "+f"(d[125]), "+f"(d[126]), "+f"(d[127])
    : "r"(a0), "r"(a1), "r"(a2), "r"(a3), "l"(db));
}
__device__ __forceinline__ void wgmma_rs_n64_keep(float (&d)[32], uint32_t a0, uint32_t a1, uint32_t a2, uint32_t a3, uint64_t db) {
  asm volatile("{ .reg .pred p; setp.ne.b32 p, 0, 0;\n"
    "wgmma.mma_async.sync.aligned.m64n64k16.f32.bf16.bf16 "
    "{%0, %1, %2, %3, %4, %5, %6, %7, %8, %9, %10, %11, %12, %13, %14, %15, %16, %17, %18, %19, %20, %21, %22, %23, %24, %25, %26, %27, %28, %29, %30, "
    "%31}, "
    "{%32, %33, %34, %35}, %36, p, 1, 1, 1; }"
    : "+f"(d[0]), "+f"(d[1]), "+f"(d[2]), "+f"(d[3]), "+f"(d[4]), "+f"(d[5]), "+f"(d[6]), "+f"(d[7]), "+f"(d[8]), "+f"(d[9]), "+f"(d[10]), "+f"(d[11]),
      "+f"(d[12]), "+f"(d[13]), "+f"(d[14]), "+f"(d[15]), "+f"(d[16]), "+f"(d[17]), "+f"(d[18]), "+f"(d[19]), "+f"(d[20]), "+f"(d[21]), "+f"(d[22]),
      "+f"(d[23]), "+f"(d[24]), "+f"(d[25]), "+f"(d[26]), "+f"(d[27]), "+f"(d[28]), "+f"(d[29]), "+f"(d[30]), "+f"(d[31])
    : "r"(a0), "r"(a1), "r"(a2), "r"(a3), "l"(db));
}
__device__ __forceinline__ void wgmma_rs_n64(float (&d)[32], uint32_t a0, uint32_t a1, uint32_t a2, uint32_t a3, uint64_t db) {
  asm volatile("{ .reg .pred p; setp.ne.b32 p, 1, 0;\n"
    "wgmma.mma_async.sync.aligned.m64n64k16.f32.bf16.bf16 "
    "{%0, %1, %2, %3, %4, %5, %6, %7, %8, %9, %10, %11, %12, %13, %14, %15, %16, %17, %18, %19, %20, %21, %22, %23, %24, %25, %26, %27, %28, %29, %30, "
    "%31}, "
    "{%32, %33, %34, %35}, %36, p, 1, 1, 1; }"
    : "+f"(d[0]), "+f"(d[1]), "+f"(d[2]), "+f"(d[3]), "+f"(d[4]), "+f"(d[5]), "+f"(d[6]), "+f"(d[7]), "+f"(d[8]), "+f"(d[9]), "+f"(d[10]), "+f"(d[11]),
      "+f"(d[12]), "+f"(d[13]), "+f"(d[14]), "+f"(d[15]), "+f"(d[16]), "+f"(d[17]), "+f"(d[18]), "+f"(d[19]), "+f"(d[20]), "+f"(d[21]), "+f"(d[22]),
      "+f"(d[23]), "+f"(d[24]), "+f"(d[25]), "+f"(d[26]), "+f"(d[27]), "+f"(d[28]), "+f"(d[29]), "+f"(d[30]), "+f"(d[31])
    : "r"(a0), "r"(a1), "r"(a2), "r"(a3), "l"(db));
}
__device__ __forceinline__ void wgmma_rs_n64k_init(float (&d)[32], uint32_t a0, uint32_t a1, uint32_t a2, uint32_t a3, uint64_t db) {
  asm volatile("{ .reg .pred p; setp.ne.b32 p, 0, 0;\n"
    "wgmma.mma_async.sync.aligned.m64n64k16.f32.bf16.bf16 "
    "{%0, %1, %2, %3, %4, %5, %6, %7, %8, %9, %10, %11, %12, %13, %14, %15, %16, %17, %18, %19, %20, %21, %22, %23, %24, %25, %26, %27, %28, %29, %30, "
    "%31}, "
    "{%32, %33, %34, %35}, %36, p, 1, 1, 0; }"
    : "=f"(d[0]), "=f"(d[1]), "=f"(d[2]), "=f"(d[3]), "=f"(d[4]), "=f"(d[5]), "=f"(d[6]), "=f"(d[7]), "=f"(d[8]), "=f"(d[9]), "=f"(d[10]), "=f"(d[11]),
      "=f"(d[12]), "=f"(d[13]), "=f"(d[14]), "=f"(d[15]), "=f"(d[16]), "=f"(d[17]), "=f"(d[18]), "=f"(d[19]), "=f"(d[20]), "=f"(d[21]), "=f"(d[22]),
      "=f"(d[23]), "=f"(d[24]), "=f"(d[25]), "=f"(d[26]), "=f"(d[27]), "=f"(d[28]), "=f"(d[29]), "=f"(d[30]), "=f"(d[31])
    : "r"(a0), "r"(a1), "r"(a2), "r"(a3), "l"(db));
}
__device__ __forceinline__ void wgmma_rs_n64k(float (&d)[32], uint32_t a0, uint32_t a1, uint32_t a2, uint32_t a3, uint64_t db) {
  asm volatile("{ .reg .pred p; setp.ne.b32 p, 1, 0;\n"
    "wgmma.mma_async.sync.aligned.m64n64k16.f32.bf16.bf16 "
    "{%0, %1, %2, %3, %4, %5, %6, %7, %8, %9, %10, %11, %12, %13, %14, %15, %16, %17, %18, %19, %20, %21, %22, %23, %24, %25, %26, %27, %28, %29, %30, "
    "%31}, "
    "{%32, %33, %34, %35}, %36, p, 1, 1, 0; }"
    : "+f"(d[0]), "+f"(d[1]), "+f"(d[2]), "+f"(d[3]), "+f"(d[4]), "+f"(d[5]), "+f"(d[6]), "+f"(d[7]), "+f"(d[8]), "+f"(d[9]), "+f"(d[10]), "+f"(d[11]),
      "+f"(d[12]), "+f"(d[13]), "+f"(d[14]), "+f"(d[15]), "+f"(d[16]), "+f"(d[17]), "+f"(d[18]), "+f"(d[19]), "+f"(d[20]), "+f"(d[21]), "+f"(d[22]),
      "+f"(d[23]), "+f"(d[24]), "+f"(d[25]), "+f"(d[26]), "+f"(d[27]), "+f"(d[28]), "+f"(d[29]), "+f"(d[30]), "+f"(d[31])
    : "r"(a0), "r"(a1), "r"(a2), "r"(a3), "l"(db));
}
__device__ __forceinline__ void wgmma_rs_n8_init(float (&d)[4], uint32_t a0, uint32_t a1, uint32_t a2, uint32_t a3, uint64_t db) {
  asm volatile("{ .reg .pred p; setp.ne.b32 p, 0, 0;\n"
    "wgmma.mma_async.sync.aligned.m64n8k16.f32.bf16.bf16 "
    "{%0, %1, %2, %3}, "
    "{%4, %5, %6, %7}, %8, p, 1, 1, 0; }"
    : "=f"(d[0]), "=f"(d[1]), "=f"(d[2]), "=f"(d[3])
    : "r"(a0), "r"(a1), "r"(a2), "r"(a3), "l"(db));
}
__device__ __forceinline__ void wgmma_rs_n8(float (&d)[4], uint32_t a0, uint32_t a1, uint32_t a2, uint32_t a3, uint64_t db) {
  asm volatile("{ .reg .pred p; setp.ne.b32 p, 1, 0;\n"
    "wgmma.mma_async.sync.aligned.m64n8k16.f32.bf16.bf16 "
    "{%0, %1, %2, %3}, "
    "{%4, %5, %6, %7}, %8, p, 1, 1, 0; }"
    : "+f"(d[0]), "+f"(d[1]), "+f"(d[2]), "+f"(d[3])
    : "r"(a0), "r"(a1), "r"(a2), "r"(a3), "l"(db));
}

__device__ __forceinline__ uint32_t kslot_off(int r) { return r == 0 ? OFF_PROJ + 16384 : r == 1 ? OFF_X2 : OFF_X1; }
__device__ __forceinline__ uint32_t kslot_stride(int r) { return r == 0 ? 32768u : 8192u; }
__device__ __forceinline__ uint32_t vslot_off(int r) { return r == 0 ? OFF_PROJ + 24576 : OFF_X0; }
__device__ __forceinline__ uint32_t vslot_stride(int r) { return r == 0 ? 32768u : 8192u; }

__device__ __forceinline__ void sum_sq(const uint4& v, float& s0, float& s1) {
  uint32_t x;
  asm("mul.rn.bf16x2 %0, %1, %1;" : "=r"(x) : "r"(v.x));
  asm("fma.rn.bf16x2 %0, %1, %1, %0;" : "+r"(x) : "r"(v.y));
  asm("fma.rn.bf16x2 %0, %1, %1, %0;" : "+r"(x) : "r"(v.z));
  asm("fma.rn.bf16x2 %0, %1, %1, %0;" : "+r"(x) : "r"(v.w));
  s0 += bf_lo(x);
  s1 += bf_hi(x);
}

__device__ __forceinline__ void query_norms_half(uint32_t half_tile, int j, int lane, float (&sum)[3]) {
  const int r = lane & 7;
  const uint32_t a = half_tile + (lane >> 4) * 8192 + r * 128 + (((((lane >> 3) & 1) << 2) ^ r) << 4) + j * 1024;
  const bool third = j < 2;
  uint4 v[6];
#pragma unroll
  for (int n = 0; n < 6; n++) v[n] = lds128((a + (n >> 2) * 3072) ^ ((n & 3) << 4));
#pragma unroll
  for (int grp = 0; grp < 3; grp++) {
    float s0 = 0.f, s1 = 0.f;
#pragma unroll
    for (int c = 0; c < 4; c++) {
      const int n = grp * 4 + c, nn = n + 6;
      sum_sq(v[n % 6], s0, s1);
      if (nn < 8 || (nn < 12 && third)) v[n % 6] = lds128((a + (nn >> 2) * 3072) ^ ((nn & 3) << 4));
    }
    sum[grp] += s0 + s1;
  }
}
__device__ __forceinline__ void query_norms_finish(float (&sum)[3], uint32_t dst, int j, int lane) {
#pragma unroll
  for (int m = 8; m <= 16; m <<= 1) {
#pragma unroll
    for (int grp = 0; grp < 3; grp++) sum[grp] += __shfl_xor_sync(0xffffffffu, sum[grp], m);
  }
  const int grp = lane >> 3;
  if (grp < 2 || (grp == 2 && j < 2)) {
    const float o = fmaf(grp == 0 ? sum[0] : grp == 1 ? sum[1] : sum[2], kNormScale, kFeatShift);
    asm volatile("st.shared.f32 [%0], %1;" ::"r"(dst + ((j + grp * 3) * 8 + (lane & 7)) * 4), "f"(o) : "memory");
  }
}

__device__ __forceinline__ void key_norms(uint32_t tile, uint32_t stride, int row0, int j, int lane, uint32_t dst, uint32_t rdst,
                                          uint32_t rbar) {
  const int row = row0 + j * 4 + (lane & 3);
  uint32_t a = tile + (lane >> 3) * stride + row * 128 + (((((lane >> 2) & 1) << 2) ^ (row & 7)) << 4);
  float sum[3];
  uint4 v0 = lds128(a), v1 = lds128(a ^ 16), v2 = lds128(a ^ 32), v3 = lds128(a ^ 48);
#pragma unroll
  for (int n = 0; n < 3; n++) {
    const bool more = n == 0 || (n == 1 && j < 2);
    float s0 = 0.f, s1 = 0.f;
    a = (a + 12 * 128) ^ 64;
    sum_sq(v0, s0, s1); if (more) v0 = lds128(a);
    sum_sq(v1, s0, s1); if (more) v1 = lds128(a ^ 16);
    sum_sq(v2, s0, s1); if (more) v2 = lds128(a ^ 32);
    sum_sq(v3, s0, s1); if (more) v3 = lds128(a ^ 48);
    sum[n] = s0 + s1;
  }
#pragma unroll
  for (int m = 4; m <= 16; m <<= 1) {
#pragma unroll
    for (int n = 0; n < 3; n++) sum[n] += __shfl_xor_sync(0xffffffffu, sum[n], m);
  }
  const int n = lane >> 2;
  if (n < 2 || (n == 2 && j < 2)) {
    const float o = fmaf(n == 0 ? sum[0] : n == 1 ? sum[1] : sum[2], kNormScale, kFeatShift);
    const uint32_t e = (row + n * 12) * 4;
    asm volatile("st.shared.f32 [%0], %1;" ::"r"(dst + e), "f"(o) : "memory");
    asm volatile("st.async.weak.shared::cluster.mbarrier::complete_tx::bytes.f32 [%0], %1, [%2];"
                 ::"r"(rdst + e), "f"(o), "r"(rbar) : "memory");
  }
}

__device__ __forceinline__ void stage_slab(uint32_t row0, const uint32_t (&pk)[64], int n, int g, int t) {
#pragma unroll
  for (int jj = 0; jj < 2; jj++) {
    const uint32_t* w = &pk[(2 * n + jj) * 8];
    const uint32_t a = row0 + ((((jj << 2) | t) ^ g) << 4);
    sts128(a, w[0], w[1], w[2], w[3]);
    sts128(a + 1024, w[4], w[5], w[6], w[7]);
  }
}

constexpr int kRegSteps = 6;
__device__ __forceinline__ void load_proj_frags(uint32_t (&a)[4 * kRegSteps], uint32_t rows16, int lane) {
  const uint32_t base = rows16 + ((lane & 7) + ((lane >> 3) & 1) * 8) * 128;
#pragma unroll
  for (int i = 0; i < kRegSteps; i++) {
    const int k = 2 * i;
    asm volatile("ldmatrix.sync.aligned.m8n8.x4.shared.b16 {%0, %1, %2, %3}, [%4];"
                 : "=r"(a[4 * i]), "=r"(a[4 * i + 1]), "=r"(a[4 * i + 2]), "=r"(a[4 * i + 3])
                 : "r"(base + (k >> 2) * 32768 + ((((k & 3) * 2 + (lane >> 4)) ^ (lane & 7)) << 4)));
  }
}
__device__ __forceinline__ void issue_g1(float (&s)[32], const uint32_t (&a)[4 * kRegSteps], uint64_t dproj, uint32_t ktile,
                                         uint32_t kstride, int w) {
  const uint64_t dk0 = make_desc(ktile, 16, 1024);
  const uint64_t st = kstride >> 4;
  const uint64_t dk1 = dk0 + st, dk2 = dk1 + st, dk3 = dk2 + st;
  wg_fence();
  wgmma_rs_n64k_init(s, a[0], a[1], a[2], a[3], dk0);
#pragma unroll
  for (int k = 1; k < 16; k++) {
    if (k == 10) turn_pass(w);
    const uint64_t dk = (k >> 2) == 0 ? dk0 : (k >> 2) == 1 ? dk1 : (k >> 2) == 2 ? dk2 : dk3;
    const int r = (k >> 1) < kRegSteps ? (k >> 1) : 0;
    if ((k & 1) == 0 && (k >> 1) < kRegSteps) wgmma_rs_n64k(s, a[4 * r], a[4 * r + 1], a[4 * r + 2], a[4 * r + 3], desc_add(dk, (k & 3) * 32));
    else wgmma_ss_n64(s, desc_add(dproj, (k >> 2) * 32768 + (k & 3) * 32), desc_add(dk, (k & 3) * 32));
  }
  wg_commit();
}
__device__ __forceinline__ void issue_g2(float (&o)[128], const uint32_t (&p)[16], uint32_t vtile, uint32_t vstride) {
  const uint64_t dv = make_desc(vtile, vstride, 1024);
  wg_fence();
#pragma unroll
  for (int k = 0; k < 4; k++) wgmma_rs_n256(o, p[4 * k], p[4 * k + 1], p[4 * k + 2], p[4 * k + 3], desc_add(dv, k * 2048));
  wg_commit();
}
__device__ __forceinline__ void load_key_offsets(float2 (&off)[8], uint32_t kn) {
#pragma unroll
  for (int j = 0; j < 8; j++) off[j] = lds64f(kn + j * 32);
}
__device__ __forceinline__ void key_features(const float (&s)[32], uint32_t (&p)[16], const float2 (&off)[8], float& ks0, float& ks1) {
#pragma unroll
  for (int j = 0; j < 8; j++) {
    const float e0 = ex2(fmaf(s[4 * j + 0], kDotScale, -off[j].x)), e1 = ex2(fmaf(s[4 * j + 1], kDotScale, -off[j].y));
    const float e2 = ex2(fmaf(s[4 * j + 2], kDotScale, -off[j].x)), e3 = ex2(fmaf(s[4 * j + 3], kDotScale, -off[j].y));
    ks0 += e0 + e1;
    ks1 += e2 + e3;
    p[2 * j + 0] = pack_bf16(e0, e1);
    p[2 * j + 1] = pack_bf16(e2, e3);
  }
}

template <bool kFirst>
__device__ __forceinline__ void issue_g3(float (&s)[128], uint32_t qtile, uint32_t proj, int w, bool pass, uint32_t hi_bar,
                                         uint32_t lo_free, int lane) {
  const uint64_t da = make_desc(qtile, 16, 1024), db = make_desc(proj, 16, 1024);
  wg_fence();
  wgmma_ss_n256_init(s, da, db);
#pragma unroll
  for (int k = 1; k < 16; k++) {
    if (k == 15 && pass) turn_pass(w);
    if (k == 8) mbar_wait_warp<1>(hi_bar);
    wgmma_ss_n256(s, desc_add(da, (k >> 2) * 8192 + (k & 3) * 32), desc_add(db, (k >> 2) * 32768 + (k & 3) * 32));
    if (kFirst && k == 7) wg_commit();
    if (kFirst && k == 9) {
      wg_commit();
      wg_wait1();
      if (w == 1 && lane == 0) mbar_arrive(lo_free);
    }
  }
  wg_commit();
}

__device__ __forceinline__ float after(float x, uint32_t dep, uint32_t sel) {
  uint32_t r;
  asm("prmt.b32 %0, %1, %2, %3;" : "=r"(r) : "r"(__float_as_uint(x)), "r"(dep), "r"(sel));
  return __uint_as_float(r);
}
__device__ __forceinline__ void feature_map(const float (&s)[128], uint32_t (&p)[64], float off0, float off1, uint32_t sel) {
#pragma unroll
  for (int c = 0; c < 8; c++) {
    if (c) {
      const int jd = 31 - (c - 1) * 4;
      off0 = after(off0, p[2 * jd], sel);
      off1 = after(off1, p[2 * jd + 1], sel);
    }
#pragma unroll
    for (int jj = 0; jj < 4; jj++) {
      const int j = 31 - (c * 4 + jj);
      const float e0 = ex2(fmaf(s[4 * j + 0], kDotScale, -off0)), e1 = ex2(fmaf(s[4 * j + 1], kDotScale, -off0));
      const float e2 = ex2(fmaf(s[4 * j + 2], kDotScale, -off1)), e3 = ex2(fmaf(s[4 * j + 3], kDotScale, -off1));
      p[2 * j + 0] = pack_bf16(e0, e1);
      p[2 * j + 1] = pack_bf16(e2, e3);
    }
  }
}

__device__ __forceinline__ void issue_g4(float (&o)[32], const uint32_t (&p)[64], uint32_t slab) {
  const uint64_t db = make_desc(slab, 16, 1024);
  wgmma_rs_n64_keep(o, p[0], p[1], p[2], p[3], db);
#pragma unroll
  for (int k = 1; k < 16; k++) wgmma_rs_n64(o, p[4 * k], p[4 * k + 1], p[4 * k + 2], p[4 * k + 3], desc_add(db, k * 2048));
}
__device__ __forceinline__ void issue_den(float (&d)[4], const uint32_t (&p)[64], uint32_t ksum) {
  const uint64_t db = make_vec_desc(ksum);
  wgmma_rs_n8_init(d, p[0], p[1], p[2], p[3], db);
#pragma unroll
  for (int k = 1; k < 16; k++) wgmma_rs_n8(d, p[4 * k], p[4 * k + 1], p[4 * k + 2], p[4 * k + 3], desc_add(db, k * 32));
}
__device__ __forceinline__ void den_to_scale(const float (&d)[4], int lane, float& r0, float& r1) {
  r0 = rcp(__shfl_sync(0xffffffffu, d[0], lane & ~3) + 1e-6f);
  r1 = rcp(__shfl_sync(0xffffffffu, d[2], lane & ~3) + 1e-6f);
}
__device__ __forceinline__ void store_slab(const float (&o)[32], float r0, float r1, __nv_bfloat16* out_row) {
#pragma unroll
  for (int J = 0; J < 2; J++) {
    uint4 v0, v1;
    v0.x = pack_bf16(o[16 * J + 0] * r0, o[16 * J + 1] * r0);
    v0.y = pack_bf16(o[16 * J + 4] * r0, o[16 * J + 5] * r0);
    v0.z = pack_bf16(o[16 * J + 8] * r0, o[16 * J + 9] * r0);
    v0.w = pack_bf16(o[16 * J + 12] * r0, o[16 * J + 13] * r0);
    v1.x = pack_bf16(o[16 * J + 2] * r1, o[16 * J + 3] * r1);
    v1.y = pack_bf16(o[16 * J + 6] * r1, o[16 * J + 7] * r1);
    v1.z = pack_bf16(o[16 * J + 10] * r1, o[16 * J + 11] * r1);
    v1.w = pack_bf16(o[16 * J + 14] * r1, o[16 * J + 15] * r1);
    __stcs(reinterpret_cast<uint4*>(out_row + J * 32), v0);
    __stcs(reinterpret_cast<uint4*>(out_row + 8 * kDim + J * 32), v1);
  }
}

struct Maps { CUtensorMap q2, k3, v3, k, v, p; };

__global__ void __cluster_dims__(2, 1, 1) __launch_bounds__(kThreads, 1)
performer_kernel(const __grid_constant__ Maps tm, const __nv_bfloat16* __restrict__ q, __nv_bfloat16* __restrict__ out) {
  extern __shared__ __align__(1024) uint8_t smem[];
  const uint32_t sb = smem_u32(smem);
  const uint32_t bars = sb + OFF_BAR;
  auto bar = [&](uint32_t i) { return bars + i * 8; };

  const int tid = threadIdx.x, lane = tid & 31;
  const int warp = __shfl_sync(0xffffffffu, tid >> 5, 0);
  const int h = blockIdx.x >> 3, j8 = blockIdx.x & 7, mh = j8 & 1, sq = j8 >> 1;
  const int krow0 = h * kSeq + sq * 512;
  const int qrow0 = h * kSeq + j8 * 256;

  if (lane == 0) {
    if (warp < 8) {
      mbar_init(bar(B_FULLK + warp), 1);
      mbar_init(bar(B_FULLV + warp), 1);
      mbar_init(bar(B_EMPTYK + warp), 11);
      mbar_init(bar(B_EMPTYV + warp), 8);
      mbar_init(bar(B_KN + warp), 3);
    } else {
      const int i = warp - 8;
      mbar_init(bar(B_FULLQ + i), 1);
      mbar_init(bar(B_EMPTYQ + i), 7);
      mbar_init(bar(B_QN + i), 3);
      mbar_init(bar(B_KV + i), 1);
      mbar_init(bar(B_STG + i), 4);
      if (i == 3) mbar_init(bar(B_QLO), 7);
      if (i < 2) mbar_init(bar(B_PROJA + i), 1 + i);
    }
    asm volatile("fence.mbarrier_init.release.cluster;" ::: "memory");
    if (warp == 8) {
#pragma unroll
      for (int i = 0; i < 6; i++) asm volatile("prefetch.tensormap [%0];" ::"l"(&tm.q2 + i) : "memory");
    }
  }
  if (warp == 1) {
    sts128(sb + OFF_KSUM + lane * 16, 0, 0, 0, 0);
    fence_async_smem();
  }
  __syncthreads();
  asm volatile("barrier.cluster.arrive.relaxed.aligned;" ::: "memory");

  uint8_t* const kv_head = reinterpret_cast<uint8_t*>(g_kv) + (size_t)h * 131072;

  if (warp >= 8) {
    asm volatile("setmaxnreg.dec.sync.aligned.u32 40;");
    if (warp == 8) {
      if (lane == 0) {
        tma_tile<true>(sb + kslot_off(0), 32768, &tm.k, krow0, bar(B_FULLK + 0));
        mbar_expect_tx(bar(B_PROJA), 65536);
#pragma unroll
        for (int j = 0; j < 4; j++) {
          tma_box(sb + OFF_PROJ + j * 32768, &tm.p, j * 64, mh * 128, bar(B_PROJA));
          tma_box(sb + OFF_PROJ + j * 32768 + 8192, &tm.p, j * 64, mh * 128 + 64, bar(B_PROJA));
        }
        tma_tile<true>(sb + vslot_off(0), 32768, &tm.v, krow0, bar(B_FULLV + 0));
        tma_tile3(sb + kslot_off(1), &tm.k3, krow0 + 64, bar(B_FULLK + 1));
        tma_tile3(sb + vslot_off(1), &tm.v3, krow0 + 64, bar(B_FULLV + 1));
        tma_tile3(sb + kslot_off(2), &tm.k3, krow0 + 128, bar(B_FULLK + 2));
        const unsigned epoch = g_epoch[blockIdx.x];
        const unsigned target = (epoch + 1) * 8;
        unsigned* flags = g_flag + h * 4;
        int rk = 0;
        for (int i = 0; i < 6; i++) {
          if (i < 5) {
            mbar_wait(bar(B_EMPTYK + i));
            if (rk == 0) tma_tile<true>(sb + kslot_off(0), 32768, &tm.k, krow0 + (i + 3) * 64, bar(B_FULLK + i + 3));
            else tma_tile3(sb + kslot_off(rk), &tm.k3, krow0 + (i + 3) * 64, bar(B_FULLK + i + 3));
            rk = rk == 2 ? 0 : rk + 1;
          }
          if (i == 5) {
            mbar_wait(bar(B_EMPTYK + 5));
            tma_half_tile(sb + OFF_X1, &tm.q2, qrow0, 0, bar(B_FULLQ + 0));
          }
          mbar_wait(bar(B_EMPTYV + i));
          if ((i & 1) == 0) tma_tile<true>(sb + vslot_off(0), 32768, &tm.v, krow0 + (i + 2) * 64, bar(B_FULLV + i + 2));
          else tma_tile3(sb + vslot_off(1), &tm.v3, krow0 + (i + 2) * 64, bar(B_FULLV + i + 2));
        }
        tma_half_tile(sb + OFF_X1 + 16384, &tm.q2, qrow0, 2, bar(B_FULLQH + 0));
        const int prow = (1 - mh) * 128;
        mbar_wait(bar(B_EMPTYK + 6));
        tma_tile<false>(sb + kslot_off(0), 32768, &tm.p, prow, bar(B_PROJB));
        mbar_wait(bar(B_EMPTYV + 6));
        tma_tile<false>(sb + vslot_off(0), 32768, &tm.p, prow + 64, bar(B_PROJB));
        mbar_wait(bar(B_EMPTYK + 7));
        tma_half_tile(sb + OFF_X2, &tm.q2, qrow0 + 64, 0, bar(B_FULLQ + 1));
        tma_half_tile(sb + OFF_X2 + 16384, &tm.q2, qrow0 + 64, 2, bar(B_FULLQH + 1));
        uint8_t* const kv_own = kv_head + mh * 16384;
        flag_wait(flags + 0, target);
        mbar_wait(bar(B_STG + 0));
        bulk_reduce_bf16(kv_own, sb + OFF_X0, 8192);
        bulk_reduce_bf16(kv_own + 32768, sb + OFF_X0 + 8192, 8192);
        bulk_reduce_bf16(g_ksum + h * 256 + mh * 128, sb + OFF_KSUM, 128);
        bulk_commit();
        mbar_wait(bar(B_STG + 1));
        bulk_reduce_bf16(kv_own + 8192, sb + OFF_X0 + 16384, 8192);
        bulk_reduce_bf16(kv_own + 32768 + 8192, sb + OFF_X0 + 16384 + 8192, 8192);
        bulk_reduce_bf16(g_ksum + h * 256 + mh * 128 + 64, sb + OFF_KSUM + 128, 128);
        bulk_commit();
        bulk_wait_read<1>();
        tma_half_tile(sb + OFF_X0, &tm.q2, qrow0 + 128, 0, bar(B_FULLQ + 2));
        bulk_wait_read<0>();
        tma_half_tile(sb + OFF_X0 + 16384, &tm.q2, qrow0 + 128, 2, bar(B_FULLQH + 2));
        mbar_wait(bar(B_EMPTYQ + 0));
        tma_half_tile(sb + OFF_X1, &tm.q2, qrow0 + 192, 0, bar(B_FULLQ + 3));
        tma_half_tile(sb + OFF_X1 + 16384, &tm.q2, qrow0 + 192, 2, bar(B_FULLQH + 3));
        bulk_wait_all();
        flag_publish(flags + 1);
        mbar_wait(bar(B_STG + 2));
        bulk_reduce_bf16(kv_own + 2 * 32768, sb + OFF_X2, 8192);
        bulk_reduce_bf16(kv_own + 3 * 32768, sb + OFF_X2 + 8192, 8192);
        bulk_commit();
        flag_wait(flags + 1, target);
        const uint32_t own = mh * 16384, oth = (1 - mh) * 16384;
        mbar_wait(bar(B_EMPTYQ + 2));
        mbar_expect_tx(bar(B_KV + 0), 32768 + 512);
        bulk_load(sb + OFF_X0, kv_head + own, 16384, bar(B_KV + 0));
        bulk_load(sb + OFF_X0 + 16384, kv_head + oth, 16384, bar(B_KV + 0));
        bulk_load(sb + OFF_KSUM, g_ksum + h * 256 + mh * 128, 256, bar(B_KV + 0));
        bulk_load(sb + OFF_KSUM + 256, g_ksum + h * 256 + (1 - mh) * 128, 256, bar(B_KV + 0));
        mbar_wait(bar(B_STG + 3));
        bulk_reduce_bf16(kv_own + 2 * 32768 + 8192, sb + OFF_X2 + 16384, 8192);
        bulk_reduce_bf16(kv_own + 3 * 32768 + 8192, sb + OFF_X2 + 16384 + 8192, 8192);
        bulk_commit();
        bulk_wait_all();
        flag_publish(flags + 2);
        mbar_wait(bar(B_EMPTYQ + 3));
        mbar_expect_tx(bar(B_KV + 1), 32768);
        bulk_load(sb + OFF_X1, kv_head + 32768 + own, 16384, bar(B_KV + 1));
        bulk_load(sb + OFF_X1 + 16384, kv_head + 32768 + oth, 16384, bar(B_KV + 1));
        flag_wait(flags + 2, target);
#pragma unroll
        for (int n = 2; n < 4; n++) {
          mbar_expect_tx(bar(B_KV + n), 32768);
          bulk_load(sb + OFF_PROJ + (n - 2) * 32768, kv_head + n * 32768 + own, 16384, bar(B_KV + n));
          bulk_load(sb + OFF_PROJ + (n - 2) * 32768 + 16384, kv_head + n * 32768 + oth, 16384, bar(B_KV + n));
        }
        g_epoch[blockIdx.x] = epoch + 1;
      }
    } else {
      uint32_t rkn, rbars;
      asm volatile("mapa.shared::cluster.u32 %0, %1, %2;" : "=r"(rkn) : "r"(sb + OFF_KN), "r"(mh ^ 1));
      asm volatile("mapa.shared::cluster.u32 %0, %1, %2;" : "=r"(rbars) : "r"(bars), "r"(mh ^ 1));
      asm volatile("barrier.cluster.wait.acquire.aligned;" ::: "memory");
      int rk = 0;
      for (int i = 0; i < 8; i++) {
        mbar_wait_warp(bar(B_FULLK + i));
        key_norms(sb + kslot_off(rk), kslot_stride(rk), 32 * mh, warp - 9, lane, sb + OFF_KN + i * 256, rkn + i * 256,
                  rbars + (B_KN + i) * 8);
        __syncwarp();
        if (lane == 0) {
          if (warp == 9) mbar_expect_tx(bar(B_KN + i), 128);
          else mbar_arrive(bar(B_KN + i));
          mbar_arrive(bar(B_EMPTYK + i));
        }
        rk = rk == 2 ? 0 : rk + 1;
        if (warp == 11 && lane == 0) {
          if (i == 2) {
            for (int n = 0; n < 32; n++) bulk_store(kv_head + j8 * 16384 + n * 512, sb + OFF_KSUM, 512);
            bulk_store(g_ksum + h * 256 + j8 * 32, sb + OFF_KSUM, 64);
            bulk_commit();
          } else if (i == 4) {
            bulk_wait_all();
            flag_publish(g_flag + h * 4);
          }
        }
        __syncwarp();
      }
#pragma unroll 1
      for (int i = 0; i < 4; i++) {
        const uint32_t tile = sb + (i == 1 ? OFF_X2 : i == 2 ? OFF_X0 : OFF_X1);
        float sum[3] = {0.f, 0.f, 0.f};
        mbar_wait_warp(bar(B_FULLQ + i));
        if (i == 1) {
          const uint8_t* qp = reinterpret_cast<const uint8_t*>(q + (size_t)(qrow0 + 128) * kDim);
          for (int o = (tid - 288) * 128; o < 32768; o += 96 * 128) asm volatile("prefetch.global.L2 [%0];" ::"l"(qp + o));
        }
        query_norms_half(tile, warp - 9, lane, sum);
        if (i == 1) {
          __syncwarp();
          if (lane == 0) mbar_arrive(bar(B_QLO));
        }
        mbar_wait_warp<1>(bar(B_FULLQH + i));
        query_norms_half(tile + 16384, warp - 9, lane, sum);
        query_norms_finish(sum, sb + OFF_KN + i * 256, warp - 9, lane);
        __syncwarp();
        if (lane == 0) {
          mbar_arrive(bar(B_QN + i));
          mbar_arrive(bar(B_EMPTYQ + i));
        }
      }
    }
  } else {
    asm volatile("setmaxnreg.inc.sync.aligned.u32 232;");
    const int w = warp >> 2, wi = warp & 3, g = lane >> 2, t = lane & 3;
    uint32_t pk[64];
    {
      float o[128];
#pragma unroll
      for (int i = 0; i < 128; i++) o[i] = 0.f;
      float ks0 = 0.f, ks1 = 0.f;
      uint32_t p[16];
      const uint64_t dproj = make_desc(sb + OFF_PROJ + w * 8192, 16, 1024);
      if (w == 1) turn_pass(w);
      mbar_wait_warp(bar(B_PROJA));
      uint32_t pfrag[4 * kRegSteps];
      load_proj_frags(pfrag, sb + OFF_PROJ + w * 8192 + wi * 2048, lane);
      {
        float s[32];
        float2 off[8];
        turn_wait(w);
        mbar_wait_warp(bar(B_FULLK + 0));
        issue_g1(s, pfrag, dproj, sb + kslot_off(0), 32768, w);
        wg_wait0();
        pin(s);
        if (lane == 0) mbar_arrive(bar(B_EMPTYK + 0));
        mbar_wait_warp(bar(B_KN + 0));
        load_key_offsets(off, sb + OFF_KN + t * 8);
        key_features(s, p, off, ks0, ks1);
      }
      int rk = 1;
#pragma unroll 1
      for (int i = 1; i < 8; i++) {
        const int rv = (i - 1) & 1;
        float s[32];
        float2 off[8];
        turn_wait(w);
        mbar_wait_warp(bar(B_FULLV + i - 1));
        issue_g2(o, p, sb + vslot_off(rv), vslot_stride(rv));
        mbar_wait_warp(bar(B_FULLK + i));
        const uint32_t kn = sb + OFF_KN + i * 256 + t * 8;
        issue_g1(s, pfrag, dproj, sb + kslot_off(rk), kslot_stride(rk), w);
        wg_wait1();
        if (lane == 0) mbar_arrive(bar(B_EMPTYV + i - 1));
        wg_wait0();
        pin(s);
        pin(o);
        if (lane == 0) mbar_arrive(bar(B_EMPTYK + i));
        mbar_wait_warp(bar(B_KN + i));
        load_key_offsets(off, kn);
        key_features(s, p, off, ks0, ks1);
        rk = rk == 2 ? 0 : rk + 1;
      }
      turn_wait(w);
      mbar_wait_warp(bar(B_FULLV + 7));
      issue_g2(o, p, sb + OFF_X0, 8192);
      turn_pass(w);
      wg_wait0();
      pin(o);
      if (lane == 0) mbar_arrive(bar(B_EMPTYV + 7));
#pragma unroll
      for (int J = 0; J < 8; J++) {
#pragma unroll
        for (int i = 0; i < 4; i++) {
          pk[J * 8 + i] = pack_bf16(o[16 * J + 4 * i + 0], o[16 * J + 4 * i + 1]);
          pk[J * 8 + 4 + i] = pack_bf16(o[16 * J + 4 * i + 2], o[16 * J + 4 * i + 3]);
        }
      }
      ks0 += __shfl_xor_sync(0xffffffffu, ks0, 1);
      ks1 += __shfl_xor_sync(0xffffffffu, ks1, 1);
      ks0 += __shfl_xor_sync(0xffffffffu, ks0, 2);
      ks1 += __shfl_xor_sync(0xffffffffu, ks1, 2);
      mbar_wait_warp(bar(B_EMPTYV + 7));
      if (t == 0) {
        const uint32_t a = sb + OFF_KSUM + (w * 64 + wi * 16 + g) * 2;
        asm volatile("st.shared.b16 [%0], %1;" ::"r"(a), "h"(__bfloat16_as_ushort(__float2bfloat16(ks0))) : "memory");
        asm volatile("st.shared.b16 [%0], %1;" ::"r"(a + 16), "h"(__bfloat16_as_ushort(__float2bfloat16(ks1))) : "memory");
      }
    }
    {
      const uint32_t row0 = sb + OFF_X0 + w * 16384 + (wi * 16 + g) * 128;
      stage_slab(row0, pk, 0, g, t);
      stage_slab(row0 + 8192, pk, 1, g, t);
    }
    fence_async_smem();
    __syncwarp();
    if (lane == 0) { if (w == 0) mbar_arrive(bar(B_STG + 0)); else mbar_arrive(bar(B_STG + 1)); }

    uint32_t pa[64], pc[64];
    const uint32_t zero = gridDim.y - 1, one = gridDim.y;
    const uint32_t qtile = sb + (w == 0 ? OFF_X1 : OFF_X2);
    const uint32_t qn = sb + OFF_KN + w * 256 + (wi * 16 + g) * 4;
    {
      float s[128];
      turn_wait(w);
      mbar_wait_warp(bar(B_PROJB));
      if (w == 0) mbar_wait_warp(bar(B_FULLQ + 0)); else mbar_wait_warp(bar(B_FULLQ + 1));
      issue_g3<true>(s, qtile, sb + OFF_PROJ, w, true, bar(B_FULLQH + w), bar(B_QLO), lane);
      if (w == 0) mbar_wait_warp(bar(B_QN + 0)); else mbar_wait_warp(bar(B_QN + 1));
      const float off0 = lds32f(qn), off1 = lds32f(qn + 32);
      wg_wait0();
      pin(s);
      if (lane == 0) { if (w == 0) mbar_arrive(bar(B_EMPTYQ + 0)); else mbar_arrive(bar(B_EMPTYQ + 1)); }
      feature_map(s, pa, off0, off1, 0x320F + one);
    }
    if (w == 0) mbar_wait_warp(bar(B_QLO)); else mbar_wait_warp(bar(B_EMPTYQ + 1));
    {
      const uint32_t row2 = sb + OFF_X2 + w * 16384 + (wi * 16 + g) * 128;
      stage_slab(row2, pk, 2, g, t);
      stage_slab(row2 + 8192, pk, 3, g, t);
    }
    fence_async_smem();
    __syncwarp();
    if (lane == 0) { if (w == 0) mbar_arrive(bar(B_STG + 2)); else mbar_arrive(bar(B_STG + 3)); }
    {
      float s[128];
      turn_wait(w);
      if (w == 0) mbar_wait_warp(bar(B_FULLQ + 2)); else mbar_wait_warp(bar(B_FULLQ + 3));
      issue_g3<false>(s, sb + (w == 0 ? OFF_X0 : OFF_X1) + zero, sb + OFF_PROJ + zero, w, w == 0, bar(B_FULLQH + 2 + w), 0, lane);
      if (w == 0) mbar_wait_warp(bar(B_QN + 2)); else mbar_wait_warp(bar(B_QN + 3));
      const float off0 = lds32f(qn + 512), off1 = lds32f(qn + 512 + 32);
      wg_wait0();
      pin(s);
      if (lane == 0) { if (w == 0) mbar_arrive(bar(B_EMPTYQ + 2)); else mbar_arrive(bar(B_EMPTYQ + 3)); }
      feature_map(s, pc, off0, off1, 0x320F + one);
    }
    __nv_bfloat16* out_a = out + (size_t)(qrow0 + w * 64 + wi * 16 + g) * kDim + t * 8;
    __nv_bfloat16* out_c = out_a + 128 * kDim;
    float oa[32], oc[32];
#pragma unroll
    for (int i = 0; i < 32; i++) oa[i] = oc[i] = 0.f;
    float ra0, ra1, rc0, rc1;
    mbar_wait_warp(bar(B_KV + 0));
    {
      float da[4], dc[4];
      wg_fence();
      issue_den(da, pa, sb + OFF_KSUM);
      issue_den(dc, pc, sb + OFF_KSUM);
      wg_commit();
      issue_g4(oa, pa, sb + OFF_X0);
      wg_commit();
      wg_wait1();
      pin(da);
      pin(dc);
      den_to_scale(da, lane, ra0, ra1);
      den_to_scale(dc, lane, rc0, rc1);
    }
    wg_fence();
    issue_g4(oc, pc, sb + OFF_X0);
    wg_commit();
    wg_wait1();
    pin(oa);
    store_slab(oa, ra0, ra1, out_a);
    mbar_wait_warp(bar(B_KV + 1));
    wg_fence();
    issue_g4(oa, pa, sb + OFF_X1);
    wg_commit();
    wg_wait1();
    pin(oc);
    store_slab(oc, rc0, rc1, out_c);
#pragma unroll
    for (int n = 1; n < 4; n++) {
      const uint32_t slab = sb + (n == 1 ? OFF_X1 : OFF_PROJ + (n - 2) * 32768);
      wg_fence();
      issue_g4(oc, pc, slab);
      wg_commit();
      wg_wait1();
      pin(oa);
      store_slab(oa, ra0, ra1, out_a + n * 64);
      if (n < 3) {
        mbar_wait_warp(bar(B_KV + n + 1));
        wg_fence();
        issue_g4(oa, pa, sb + OFF_PROJ + (n - 1) * 32768);
        wg_commit();
        wg_wait1();
      } else {
        wg_wait0();
      }
      pin(oc);
      store_slab(oc, rc0, rc1, out_c + n * 64);
    }
  }
}

typedef CUresult (*EncodeTiledFn)(CUtensorMap*, CUtensorMapDataType, cuuint32_t, void*, const cuuint64_t*, const cuuint64_t*,
                                  const cuuint32_t*, const cuuint32_t*, CUtensorMapInterleave, CUtensorMapSwizzle,
                                  CUtensorMapL2promotion, CUtensorMapFloatOOBfill);

bool make_map2(EncodeTiledFn enc, CUtensorMap* m, const void* ptr, uint64_t rows) {
  const cuuint64_t dims[2] = {(cuuint64_t)kDim, rows};
  const cuuint64_t strides[1] = {kDim * 2};
  const cuuint32_t box[2] = {64, 64};
  const cuuint32_t es[2] = {1, 1};
  return enc(m, CU_TENSOR_MAP_DATA_TYPE_BFLOAT16, 2, const_cast<void*>(ptr), dims, strides, box, es, CU_TENSOR_MAP_INTERLEAVE_NONE,
             CU_TENSOR_MAP_SWIZZLE_128B, CU_TENSOR_MAP_L2_PROMOTION_L2_128B, CU_TENSOR_MAP_FLOAT_OOB_FILL_NONE) == CUDA_SUCCESS;
}
bool make_map3(EncodeTiledFn enc, CUtensorMap* m, const void* ptr, uint64_t rows, uint32_t slabs = 4) {
  const cuuint64_t dims[3] = {64, rows, 4};
  const cuuint64_t strides[2] = {kDim * 2, 128};
  const cuuint32_t box[3] = {64, 64, slabs};
  const cuuint32_t es[3] = {1, 1, 1};
  return enc(m, CU_TENSOR_MAP_DATA_TYPE_BFLOAT16, 3, const_cast<void*>(ptr), dims, strides, box, es, CU_TENSOR_MAP_INTERLEAVE_NONE,
             CU_TENSOR_MAP_SWIZZLE_128B, CU_TENSOR_MAP_L2_PROMOTION_L2_128B, CU_TENSOR_MAP_FLOAT_OOB_FILL_NONE) == CUDA_SUCCESS;
}

}

extern "C" void kernel_launch(void* const* d_in, const int* in_sizes, int n_in, void* d_out, int out_size) {
  (void)in_sizes; (void)n_in; (void)out_size;
  static EncodeTiledFn enc = nullptr;
  if (!enc) {
    void* fn = nullptr;
    cudaDriverEntryPointQueryResult qr;
    if (cudaGetDriverEntryPoint("cuTensorMapEncodeTiled", &fn, cudaEnableDefault, &qr) != cudaSuccess || !fn) return;
    enc = (EncodeTiledFn)fn;
    cudaFuncSetAttribute(performer_kernel, cudaFuncAttributeMaxDynamicSharedMemorySize, SMEM_BYTES);
  }
  const uint64_t rows = (uint64_t)kHeads * kSeq;
  Maps tm;
  if (!make_map3(enc, &tm.q2, d_in[0], rows, 2) || !make_map3(enc, &tm.k3, d_in[1], rows) || !make_map3(enc, &tm.v3, d_in[2], rows) ||
      !make_map2(enc, &tm.k, d_in[1], rows) || !make_map2(enc, &tm.v, d_in[2], rows) || !make_map2(enc, &tm.p, d_in[3], 256))
    return;
  performer_kernel<<<128, kThreads, SMEM_BYTES, cudaStreamPerThread>>>(tm, (const __nv_bfloat16*)d_in[0], (__nv_bfloat16*)d_out);
}
```
